```python
import torch

def _softmax(x, axis=-1):
    return torch.softmax(x, dim=axis)

def _gelu(x):
    return torch.nn.functional.gelu(x, approximate='tanh')

def _silu(x):
    return torch.nn.functional.silu(x)

def _sigmoid(x):
    return torch.sigmoid(x)

def _layernorm(x, axis=-1, eps=1e-05):
    m = x.mean(dim=axis, keepdim=True)
    v = x.var(dim=axis, keepdim=True, unbiased=False)
    return (x - m) / torch.sqrt(v + eps)

def _scatter_add(tgt, idx, src, axis=0):
    return tgt.clone().index_add_(axis, idx, src)

def _segment_sum(src, seg, n):
    out = torch.zeros((n,) + src.shape[1:], dtype=src.dtype)
    return out.index_add_(0, seg, src)

def _pad(x, pw):
    flat = tuple((v for pair in reversed(pw) for v in pair))
    return torch.nn.functional.pad(x, flat)
kernel_name = 'adaLN_cond__grouped_kv_mqa__glu_gated_glu__prompt'

def setup_inputs():

    _w = lambda a: (lambda t: t.to(torch.bfloat16) if t.is_floating_point() else t)(torch.as_tensor(a))

    def _A_setup():
        B, S, D, H = (1, 2048, 1024, 32)
        Dh = D // H
        return {'x': _w((lambda *s: torch.randn(*s, dtype=torch.bfloat16) * 0.05)(B, S, D)), 'wq': _w((lambda *s: torch.randn(*s, dtype=torch.bfloat16) * 0.05)(D, H * Dh)), 'wk': _w((lambda *s: torch.randn(*s, dtype=torch.bfloat16) * 0.05)(D, Dh)), 'wv': _w((lambda *s: torch.randn(*s, dtype=torch.bfloat16) * 0.05)(D, Dh)), 'wo': _w((lambda *s: torch.randn(*s, dtype=torch.bfloat16) * 0.05)(H * Dh, D))}
    _A_in = _A_setup()

    def _B_setup():
        B, S, D, F = (1, 2048, 1024, 3584)
        return {'x': _w((lambda *s: torch.randn(*s, dtype=torch.bfloat16) * 0.05)(B, S, D)), 'w_gate': _w((lambda *s: torch.randn(*s, dtype=torch.bfloat16) * 0.05)(D, F)), 'w_up': _w((lambda *s: torch.randn(*s, dtype=torch.bfloat16) * 0.05)(D, F)), 'w_down': _w((lambda *s: torch.randn(*s, dtype=torch.bfloat16) * 0.05)(F, D))}
    _B_in = _B_setup()
    return {'A_x': _A_in['x'], 'A_wq': _A_in['wq'], 'A_wk': _A_in['wk'], 'A_wv': _A_in['wv'], 'A_wo': _A_in['wo'], 'B_x': _B_in['x'], 'B_w_gate': _B_in['w_gate'], 'B_w_up': _B_in['w_up'], 'B_w_down': _B_in['w_down'], 'c': _w((lambda *s: torch.randn(*s, dtype=torch.bfloat16) * 0.2)(1, 1024) * 8.0), 'w_mod': _w((lambda *s: torch.randn(*s, dtype=torch.bfloat16) * 0.2)(1024, 6 * 1024) * 1024 ** (-0.5) * 8.0)}

def reference(A_x, A_wq, A_wk, A_wv, A_wo, B_x, B_w_gate, B_w_up, B_w_down, c, w_mod):

    def _A_ref(x, wq, wk, wv, wo):
        B, S, D = x.shape
        H = 32
        Dh = D // H
        q = (lambda x, *d: x.permute(*d))((x @ wq).reshape(B, S, H, Dh), 0, 2, 1, 3)
        k = x @ wk
        v = x @ wv
        scores = torch.einsum('bhqd,bkd->bhqk', q, k) * Dh ** (-0.5)
        p = _softmax(scores, axis=-1)
        o = torch.einsum('bhqk,bkd->bhqd', p, v)
        return (lambda x, *d: x.permute(*d))(o, 0, 2, 1, 3).reshape(B, S, H * Dh) @ wo

    def _B_ref(x, w_gate, w_up, w_down):
        g = torch.einsum('bsd,df->bsf', x, w_gate)
        u = torch.einsum('bsd,df->bsf', x, w_up)
        h = _sigmoid(g) * u
        return torch.einsum('bsf,fd->bsd', h, w_down)
    x = A_x
    mod = (_silu(c) @ w_mod).reshape(c.shape[0], 6, 1, -1)
    sa, ca, ga, sb, cb, gb = (mod[:, 0].clone(), mod[:, 1].clone(), mod[:, 2].clone(), mod[:, 3].clone(), mod[:, 4].clone(), mod[:, 5].clone())
    h = _layernorm(x, axis=-1) * (1 + ca) + sa
    x = x + ga * _A_ref(h, A_wq, A_wk, A_wv, A_wo)
    h = _layernorm(x, axis=-1) * (1 + cb) + sb
    x = x + gb * _B_ref(h, B_w_gate, B_w_up, B_w_down)
    return x
```

```cpp
#include <cuda_runtime.h>
#include <cuda_bf16.h>
#include <cuda.h>
#include <stdint.h>

namespace {

constexpr int SEQ = 2048, DM = 1024, DH = 32, FF = 3584;
typedef __nv_bfloat16 bf16;

__device__ __align__(1024) bf16 g_h1[SEQ * DM];
__device__ __align__(1024) bf16 g_k[SEQ * DH];
__device__ __align__(1024) bf16 g_v[SEQ * DH];
__device__ __align__(1024) bf16 g_o[SEQ * DM];
__device__ __align__(1024) bf16 g_x1[SEQ * DM];
__device__ __align__(1024) bf16 g_h2[SEQ * DM];
__device__ __align__(1024) bf16 g_act[SEQ * FF];
constexpr int F_H2 = 0, F_ACT = 128, F_ATT = 192, F_MOD2 = 208, F_COUNT = 209;
struct Small {
  unsigned mod1[8][2 * DM];
  float mod2[4 * DM];
  float2 stats[SEQ * 8];
  unsigned flags[F_COUNT];
  unsigned pre[17];
  unsigned done;
};
__device__ __align__(524288) Small g_small;
#define g_stats g_small.stats
#define g_flags g_small.flags
#define g_pre g_small.pre

__device__ __forceinline__ uint32_t smem_u32(const void* p) { return (uint32_t)__cvta_generic_to_shared(p); }
__device__ __forceinline__ void mbar_init(uint32_t bar, int cnt) { asm volatile("mbarrier.init.shared::cta.b64 [%0], %1;" ::"r"(bar), "r"(cnt)); }
__device__ __forceinline__ void mbar_expect_tx(uint32_t bar, uint32_t bytes) { asm volatile("mbarrier.arrive.expect_tx.shared::cta.b64 _, [%0], %1;" ::"r"(bar), "r"(bytes) : "memory"); }
__device__ __forceinline__ void mbar_arrive(uint32_t bar) { asm volatile("mbarrier.arrive.shared::cta.b64 _, [%0];" ::"r"(bar) : "memory"); }
__device__ __forceinline__ bool mbar_try(uint32_t bar, uint32_t parity) {
  uint32_t ok;
  asm volatile("{\n.reg .pred p;\nmbarrier.try_wait.parity.shared::cta.b64 p, [%1], %2;\nselp.u32 %0, 1, 0, p;\n}" : "=r"(ok) : "r"(bar), "r"(parity) : "memory");
  return ok;
}
__device__ __forceinline__ void mbar_wait(uint32_t bar, uint32_t parity) {
  if (mbar_try(bar, parity)) return;
#pragma unroll 1
  for (int i = 0; i < (1 << 24); i++) { if (mbar_try(bar, parity)) return; }
  __trap();
}
__device__ __forceinline__ void tma_load(uint32_t dst, const CUtensorMap* m, int c0, int c1, uint32_t bar) {
  asm volatile("cp.async.bulk.tensor.2d.shared::cluster.global.mbarrier::complete_tx::bytes [%0], [%1, {%3, %4}], [%2];"
               ::"r"(dst), "l"(m), "r"(bar), "r"(c0), "r"(c1) : "memory");
}
__device__ __forceinline__ void bulk_load(uint32_t dst, const void* src, uint32_t bytes, uint32_t bar) {
  asm volatile("cp.async.bulk.shared::cluster.global.mbarrier::complete_tx::bytes [%0], [%1], %2, [%3];" ::"r"(dst), "l"(src), "r"(bytes), "r"(bar) : "memory");
}
__device__ __forceinline__ void tma_prefetch(const CUtensorMap* m, int c0, int c1) {
  asm volatile("cp.async.bulk.prefetch.tensor.2d.L2.global [%0, {%1, %2}];" ::"l"(m), "r"(c0), "r"(c1) : "memory");
}
__device__ __forceinline__ void tma_store(const CUtensorMap* m, uint32_t src, int c0, int c1) {
  asm volatile("cp.async.bulk.tensor.2d.global.shared::cta.bulk_group [%0, {%2, %3}], [%1];" ::"l"(m), "r"(src), "r"(c0), "r"(c1) : "memory");
}
__device__ __forceinline__ void tma_store_commit() { asm volatile("cp.async.bulk.commit_group;" ::: "memory"); }
__device__ __forceinline__ void tma_store_wait_read() { asm volatile("cp.async.bulk.wait_group.read 0;" ::: "memory"); }
__device__ __forceinline__ void tma_store_wait_all() { asm volatile("cp.async.bulk.wait_group 0;" ::: "memory"); }
__device__ __forceinline__ void prefetch_map(const CUtensorMap* m) { asm volatile("prefetch.tensormap [%0];" ::"l"(m) : "memory"); }
__device__ __forceinline__ void fence_async_smem() { asm volatile("fence.proxy.async.shared::cta;" ::: "memory"); }
__device__ __forceinline__ void fence_bar_init() { asm volatile("fence.mbarrier_init.release.cluster;" ::: "memory"); }
__device__ __forceinline__ void named_bar(int id, int n) { asm volatile("bar.sync %0, %1;" ::"r"(id), "r"(n) : "memory"); }
__device__ __forceinline__ void flag_add(unsigned* f) { asm volatile("red.relaxed.gpu.global.add.u32 [%0], 1;" ::"l"(f) : "memory"); }
__device__ __forceinline__ void bulk_store(void* dst, uint32_t src, uint32_t bytes) {
  asm volatile("cp.async.bulk.global.shared::cta.bulk_group [%0], [%1], %2;" ::"l"(dst), "r"(src), "r"(bytes) : "memory");
}
__device__ __forceinline__ void flag_wait(const unsigned* f, unsigned target) {
#pragma unroll 1
  for (int i = 0; i < (1 << 22); i++) {
    unsigned v;
    asm volatile("ld.relaxed.gpu.global.u32 %0, [%1];" : "=r"(v) : "l"(f) : "memory");
    if (v >= target) return;
  }
  __trap();
}
__device__ __forceinline__ void fence_async_global() { asm volatile("fence.proxy.async.global;" ::: "memory"); }
__device__ __forceinline__ void l2_prefetch(const void* p, uint32_t bytes) { asm volatile("cp.async.bulk.prefetch.L2.global [%0], %1;" ::"l"(p), "r"(bytes) : "memory"); }
__device__ __forceinline__ void pdl_launch() { asm volatile("griddepcontrol.launch_dependents;"); }
__device__ __forceinline__ void pdl_wait() { asm volatile("griddepcontrol.wait;" ::: "memory"); }
__device__ __forceinline__ void wg_fence() { asm volatile("wgmma.fence.sync.aligned;" ::: "memory"); }
__device__ __forceinline__ void wg_commit() { asm volatile("wgmma.commit_group.sync.aligned;" ::: "memory"); }
template <int N> __device__ __forceinline__ void wg_wait() { asm volatile("wgmma.wait_group.sync.aligned %0;" ::"n"(N) : "memory"); }
template <int R> __device__ __forceinline__ void reg_dec() { asm volatile("setmaxnreg.dec.sync.aligned.u32 %0;" ::"n"(R)); }
template <int R> __device__ __forceinline__ void reg_inc() { asm volatile("setmaxnreg.inc.sync.aligned.u32 %0;" ::"n"(R)); }
__device__ __forceinline__ uint64_t mkdesc(uint32_t addr, uint32_t lbo, uint32_t sbo, int swz) {
  return (uint64_t)((addr & 0x3FFFF) >> 4) | ((uint64_t)((lbo >> 4) & 0x3FFF) << 16) | ((uint64_t)(sbo >> 4) << 32) | ((uint64_t)swz << 62);
}
__device__ __forceinline__ float ex2(float x) { float y; asm("ex2.approx.ftz.f32 %0, %1;" : "=f"(y) : "f"(x)); return y; }
__device__ __forceinline__ float rcp(float x) { float y; asm("rcp.approx.ftz.f32 %0, %1;" : "=f"(y) : "f"(x)); return y; }
__device__ __forceinline__ uint32_t pack_bf16(float lo, float hi) { uint32_t r; asm("cvt.rn.bf16x2.f32 %0, %1, %2;" : "=r"(r) : "f"(hi), "f"(lo)); return r; }
__device__ __forceinline__ float bf_lo(uint32_t u) { return __uint_as_float(u << 16); }
__device__ __forceinline__ float bf_hi(uint32_t u) { return __uint_as_float(u & 0xffff0000u); }
__device__ __forceinline__ float fma_sat(float a, float b, float c) { float y; asm("fma.rn.sat.f32 %0, %1, %2, %3;" : "=f"(y) : "f"(a), "f"(b), "f"(c)); return y; }
__device__ __forceinline__ void stsm_x4(uint32_t addr, uint32_t a, uint32_t b, uint32_t c, uint32_t d) {
  asm volatile("stmatrix.sync.aligned.m8n8.x4.shared.b16 [%0], {%1, %2, %3, %4};" ::"r"(addr), "r"(a), "r"(b), "r"(c), "r"(d) : "memory");
}
__device__ __forceinline__ uint4 ldg_stream(const void* p) {
  uint4 v;
  asm volatile("ld.global.nc.L1::no_allocate.v4.u32 {%0, %1, %2, %3}, [%4];" : "=r"(v.x), "=r"(v.y), "=r"(v.z), "=r"(v.w) : "l"(p) : "memory");
  return v;
}
template <int N> __device__ __forceinline__ void pin(float (&d)[N]) {
#pragma unroll
  for (int i = 0; i < N; i++) asm volatile("" : "+f"(d[i])::"memory");
}
template <int N> __device__ __forceinline__ void pinu(uint32_t* d) {
#pragma unroll
  for (int i = 0; i < N; i++) asm volatile("" : "+r"(d[i])::"memory");
}

__device__ __forceinline__ void wg_ss_n128_mn(float (&d)[64], uint64_t da, uint64_t db, int sd) {
  asm volatile("{\n.reg .pred p;\nsetp.ne.b32 p, %66, 0;\n"
    "wgmma.mma_async.sync.aligned.m64n128k16.f32.bf16.bf16 {"
    "%0, %1, %2, %3, %4, %5, %6, %7, %8, %9, %10, %11, %12, %13, %14, %15, %16, %17, %18, %19, %20, %21, %22, %23, %24, %25, %26, %27, %28, %29, %30, %31, "
    "%32, %33, %34, %35, %36, %37, %38, %39, %40, %41, %42, %43, %44, %45, %46, %47, %48, %49, %50, %51, %52, %53, %54, %55, %56, %57, %58, %59, %60, %61, "
    "%62, %63"
    "}, %64, %65, p, 1, 1, 0, 1;\n}\n"
    : "+f"(d[0]), "+f"(d[1]), "+f"(d[2]), "+f"(d[3]), "+f"(d[4]), "+f"(d[5]), "+f"(d[6]), "+f"(d[7]), "+f"(d[8]), "+f"(d[9]), "+f"(d[10]), "+f"(d[11]),
      "+f"(d[12]), "+f"(d[13]), "+f"(d[14]), "+f"(d[15]), "+f"(d[16]), "+f"(d[17]), "+f"(d[18]), "+f"(d[19]), "+f"(d[20]), "+f"(d[21]), "+f"(d[22]),
      "+f"(d[23]), "+f"(d[24]), "+f"(d[25]), "+f"(d[26]), "+f"(d[27]), "+f"(d[28]), "+f"(d[29]), "+f"(d[30]), "+f"(d[31]), "+f"(d[32]), "+f"(d[33]),
      "+f"(d[34]), "+f"(d[35]), "+f"(d[36]), "+f"(d[37]), "+f"(d[38]), "+f"(d[39]), "+f"(d[40]), "+f"(d[41]), "+f"(d[42]), "+f"(d[43]), "+f"(d[44]),
      "+f"(d[45]), "+f"(d[46]), "+f"(d[47]), "+f"(d[48]), "+f"(d[49]), "+f"(d[50]), "+f"(d[51]), "+f"(d[52]), "+f"(d[53]), "+f"(d[54]), "+f"(d[55]),
      "+f"(d[56]), "+f"(d[57]), "+f"(d[58]), "+f"(d[59]), "+f"(d[60]), "+f"(d[61]), "+f"(d[62]), "+f"(d[63])
    : "l"(da), "l"(db), "r"(sd));
}
__device__ __forceinline__ void wg_ss_n8_mn(float (&d)[4], uint64_t da, uint64_t db, int sd) {
  asm volatile("{\n.reg .pred p;\nsetp.ne.b32 p, %6, 0;\n"
    "wgmma.mma_async.sync.aligned.m64n8k16.f32.bf16.bf16 {"
    "%0, %1, %2, %3"
    "}, %4, %5, p, 1, 1, 0, 1;\n}\n"
    : "+f"(d[0]), "+f"(d[1]), "+f"(d[2]), "+f"(d[3])
    : "l"(da), "l"(db), "r"(sd));
}
__device__ __forceinline__ void wg_ss_n256_mn(float (&d)[128], uint64_t da, uint64_t db, int sd) {
  asm volatile("{\n.reg .pred p;\nsetp.ne.b32 p, %130, 0;\n"
    "wgmma.mma_async.sync.aligned.m64n256k16.f32.bf16.bf16 {"
    "%0, %1, %2, %3, %4, %5, %6, %7, %8, %9, %10, %11, %12, %13, %14, %15, %16, %17, %18, %19, %20, %21, %22, %23, %24, %25, %26, %27, %28, %29, %30, %31, "
    "%32, %33, %34, %35, %36, %37, %38, %39, %40, %41, %42, %43, %44, %45, %46, %47, %48, %49, %50, %51, %52, %53, %54, %55, %56, %57, %58, %59, %60, %61, "
    "%62, %63, %64, %65, %66, %67, %68, %69, %70, %71, %72, %73, %74, %75, %76, %77, %78, %79, %80, %81, %82, %83, %84, %85, %86, %87, %88, %89, %90, %91, "
    "%92, %93, %94, %95, %96, %97, %98, %99, %100, %101, %102, %103, %104, %105, %106, %107, %108, %109, %110, %111, %112, %113, %114, %115, %116, %117, "
    "%118, %119, %120, %121, %122, %123, %124, %125, %126, %127"
    "}, %128, %129, p, 1, 1, 0, 1;\n}\n"
    : "+f"(d[0]), "+f"(d[1]), "+f"(d[2]), "+f"(d[3]), "+f"(d[4]), "+f"(d[5]), "+f"(d[6]), "+f"(d[7]), "+f"(d[8]), "+f"(d[9]), "+f"(d[10]), "+f"(d[11]),
      "+f"(d[12]), "+f"(d[13]), "+f"(d[14]), "+f"(d[15]), "+f"(d[16]), "+f"(d[17]), "+f"(d[18]), "+f"(d[19]), "+f"(d[20]), "+f"(d[21]), "+f"(d[22]),
      "+f"(d[23]), "+f"(d[24]), "+f"(d[25]), "+f"(d[26]), "+f"(d[27]), "+f"(d[28]), "+f"(d[29]), "+f"(d[30]), "+f"(d[31]), "+f"(d[32]), "+f"(d[33]),
      "+f"(d[34]), "+f"(d[35]), "+f"(d[36]), "+f"(d[37]), "+f"(d[38]), "+f"(d[39]), "+f"(d[40]), "+f"(d[41]), "+f"(d[42]), "+f"(d[43]), "+f"(d[44]),
      "+f"(d[45]), "+f"(d[46]), "+f"(d[47]), "+f"(d[48]), "+f"(d[49]), "+f"(d[50]), "+f"(d[51]), "+f"(d[52]), "+f"(d[53]), "+f"(d[54]), "+f"(d[55]),
      "+f"(d[56]), "+f"(d[57]), "+f"(d[58]), "+f"(d[59]), "+f"(d[60]), "+f"(d[61]), "+f"(d[62]), "+f"(d[63]), "+f"(d[64]), "+f"(d[65]), "+f"(d[66]),
      "+f"(d[67]), "+f"(d[68]), "+f"(d[69]), "+f"(d[70]), "+f"(d[71]), "+f"(d[72]), "+f"(d[73]), "+f"(d[74]), "+f"(d[75]), "+f"(d[76]), "+f"(d[77]),
      "+f"(d[78]), "+f"(d[79]), "+f"(d[80]), "+f"(d[81]), "+f"(d[82]), "+f"(d[83]), "+f"(d[84]), "+f"(d[85]), "+f"(d[86]), "+f"(d[87]), "+f"(d[88]),
      "+f"(d[89]), "+f"(d[90]), "+f"(d[91]), "+f"(d[92]), "+f"(d[93]), "+f"(d[94]), "+f"(d[95]), "+f"(d[96]), "+f"(d[97]), "+f"(d[98]), "+f"(d[99]),
      "+f"(d[100]), "+f"(d[101]), "+f"(d[102]), "+f"(d[103]), "+f"(d[104]), "+f"(d[105]), "+f"(d[106]), "+f"(d[107]), "+f"(d[108]), "+f"(d[109]),
      "+f"(d[110]), "+f"(d[111]), "+f"(d[112]), "+f"(d[113]), "+f"(d[114]), "+f"(d[115]), "+f"(d[116]), "+f"(d[117]), "+f"(d[118]), "+f"(d[119]),
      "+f"(d[120]), "+f"(d[121]), "+f"(d[122]), "+f"(d[123]), "+f"(d[124]), "+f"(d[125]), "+f"(d[126]), "+f"(d[127])
    : "l"(da), "l"(db), "r"(sd));
}
__device__ __forceinline__ void wg_rs_n32_k(float (&d)[16], uint32_t a0, uint32_t a1, uint32_t a2, uint32_t a3, uint64_t db, int sd) {
  asm volatile("{\n.reg .pred p;\nsetp.ne.b32 p, %21, 0;\n"
    "wgmma.mma_async.sync.aligned.m64n32k16.f32.bf16.bf16 {"
    "%0, %1, %2, %3, %4, %5, %6, %7, %8, %9, %10, %11, %12, %13, %14, %15"
    "}, {%16,%17,%18,%19}, %20, p, 1, 1, 0;\n}\n"
    : "+f"(d[0]), "+f"(d[1]), "+f"(d[2]), "+f"(d[3]), "+f"(d[4]), "+f"(d[5]), "+f"(d[6]), "+f"(d[7]), "+f"(d[8]), "+f"(d[9]), "+f"(d[10]), "+f"(d[11]),
      "+f"(d[12]), "+f"(d[13]), "+f"(d[14]), "+f"(d[15])
    : "r"(a0), "r"(a1), "r"(a2), "r"(a3), "l"(db), "r"(sd));
}
__device__ __forceinline__ void wg_rs_n40_mn(float (&d)[20], uint32_t a0, uint32_t a1, uint32_t a2, uint32_t a3, uint64_t db, int sd) {
  asm volatile("{\n.reg .pred p;\nsetp.ne.b32 p, %25, 0;\n"
    "wgmma.mma_async.sync.aligned.m64n40k16.f32.bf16.bf16 {"
    "%0, %1, %2, %3, %4, %5, %6, %7, %8, %9, %10, %11, %12, %13, %14, %15, %16, %17, %18, %19"
    "}, {%20,%21,%22,%23}, %24, p, 1, 1, 1;\n}\n"
    : "+f"(d[0]), "+f"(d[1]), "+f"(d[2]), "+f"(d[3]), "+f"(d[4]), "+f"(d[5]), "+f"(d[6]), "+f"(d[7]), "+f"(d[8]), "+f"(d[9]), "+f"(d[10]), "+f"(d[11]),
      "+f"(d[12]), "+f"(d[13]), "+f"(d[14]), "+f"(d[15]), "+f"(d[16]), "+f"(d[17]), "+f"(d[18]), "+f"(d[19])
    : "r"(a0), "r"(a1), "r"(a2), "r"(a3), "l"(db), "r"(sd));
}

constexpr int A_BYTES = 16384, B_CHUNK = 8192;
constexpr int GEMM_THREADS = 384;

struct Ring { uint32_t s, ph; };
template <int ST> __device__ __forceinline__ void ring_next(Ring& r) { if (++r.s == ST) { r.s = 0; r.ph ^= 1; } }

template <int BN> struct Mma;
template <> struct Mma<128> { static __device__ __forceinline__ void go(float (&d)[64], uint64_t a, uint64_t b, int sd) { wg_ss_n128_mn(d, a, b, sd); } };
template <> struct Mma<256> { static __device__ __forceinline__ void go(float (&d)[128], uint64_t a, uint64_t b, int sd) { wg_ss_n256_mn(d, a, b, sd); } };

__device__ __forceinline__ void stage_store(uint32_t stg, int row_base, int lane, int jb, uint32_t r0, uint32_t r1, uint32_t r2, uint32_t r3) {
  const int i = lane >> 3, rr = lane & 7;
  const int row = row_base + (i & 1) * 8 + rr, cb = jb + (i >> 1);
  stsm_x4(stg + (cb >> 3) * 16384 + row * 128 + (((cb & 7) ^ (row & 7)) << 4), r0, r1, r2, r3);
}

constexpr int ATT_WG = 4, FRONT_THREADS = ATT_WG * 128 + 128, ATT_SLOTS = 4, ATT_SLOT = 32768;
constexpr float ATT_MARGIN = 88.f, ATT_LMAX = 8.507059e37f;
constexpr float EXP_R = 254.984375f;
constexpr uint32_t ATT_PM = 0x03020301u;

__device__ __forceinline__ uint32_t hfma2(uint32_t a, uint32_t b, uint32_t c) { uint32_t r; asm("fma.rn.bf16x2 %0, %1, %2, %3;" : "=r"(r) : "r"(a), "r"(b), "r"(c)); return r; }
__device__ __forceinline__ uint32_t exp2_pair(float sa, float sb, float bz) {
  const float za = fma_sat(sa, 1.0f / EXP_R, bz), zb = fma_sat(sb, 1.0f / EXP_R, bz);
  const float ta = fmaf(za, EXP_R / 256.f, 256.f), tb = fmaf(zb, EXP_R / 256.f, 256.f);
  uint32_t v, ng;
  asm("prmt.b32 %0, %1, %2, 0x5410;" : "=r"(v) : "r"(__float_as_uint(ta)), "r"(__float_as_uint(tb)));
  asm("lop3.b32 %0, %1, 0x007F007F, 0xBF80BF80, 0xEA;" : "=r"(ng) : "r"(v));
  uint32_t t = hfma2(ng, 0x3DF03DF0u, 0x3F253F25u);
  t = hfma2(t, ng, 0x3F523F52u);
  return hfma2(v, hfma2(ng, t, t), v);
}
template <uint32_t PM4>
__device__ __forceinline__ void softmax8(const float* s, uint32_t* p, float nm0, float nm1, float bz0, float bz1) {
#pragma unroll
  for (int i = 0; i < 4; i++) {
    const bool r1 = i & 1;
    if ((PM4 >> i) & 1) p[i] = exp2_pair(s[2 * i], s[2 * i + 1], r1 ? bz1 : bz0);
    else p[i] = pack_bf16(ex2(s[2 * i] + (r1 ? nm1 : nm0)), ex2(s[2 * i + 1] + (r1 ? nm1 : nm0)));
  }
}

__device__ __forceinline__ void attn_row_exact(const uint4* qp, bf16* orow, int lane) {
  float q[32];
#pragma unroll
  for (int c = 0; c < 4; c++) {
    const uint4 u = qp[c];
    q[2 * c] = bf_lo(u.x); q[2 * c + 1] = bf_hi(u.x); q[8 + 2 * c] = bf_lo(u.y); q[8 + 2 * c + 1] = bf_hi(u.y);
    q[16 + 2 * c] = bf_lo(u.z); q[16 + 2 * c + 1] = bf_hi(u.z); q[24 + 2 * c] = bf_lo(u.w); q[24 + 2 * c + 1] = bf_hi(u.w);
  }
  auto score = [&](int key) {
    const uint4* kp = reinterpret_cast<const uint4*>(g_k + (size_t)key * DH);
    float s = 0.f;
#pragma unroll
    for (int c = 0; c < 4; c++) {
      const uint4 u = __ldcg(kp + c);
      s += q[8 * c] * bf_lo(u.x) + q[8 * c + 1] * bf_hi(u.x) + q[8 * c + 2] * bf_lo(u.y) + q[8 * c + 3] * bf_hi(u.y);
      s += q[8 * c + 4] * bf_lo(u.z) + q[8 * c + 5] * bf_hi(u.z) + q[8 * c + 6] * bf_lo(u.w) + q[8 * c + 7] * bf_hi(u.w);
    }
    return s;
  };
  float m = -INFINITY;
#pragma unroll 1
  for (int key = lane; key < SEQ; key += 32) m = fmaxf(m, score(key));
#pragma unroll
  for (int o = 16; o > 0; o >>= 1) m = fmaxf(m, __shfl_xor_sync(~0u, m, o));
  float l = 0.f, o[32];
#pragma unroll
  for (int d = 0; d < 32; d++) o[d] = 0.f;
#pragma unroll 1
  for (int key = lane; key < SEQ; key += 32) {
    const float p = ex2(score(key) - m);
    l += p;
    const uint4* vp = reinterpret_cast<const uint4*>(g_v + (size_t)key * DH);
#pragma unroll
    for (int c = 0; c < 4; c++) {
      const uint4 u = __ldcg(vp + c);
      o[8 * c] += p * bf_lo(u.x); o[8 * c + 1] += p * bf_hi(u.x); o[8 * c + 2] += p * bf_lo(u.y); o[8 * c + 3] += p * bf_hi(u.y);
      o[8 * c + 4] += p * bf_lo(u.z); o[8 * c + 5] += p * bf_hi(u.z); o[8 * c + 6] += p * bf_lo(u.w); o[8 * c + 7] += p * bf_hi(u.w);
    }
  }
#pragma unroll
  for (int of = 16; of > 0; of >>= 1) {
    l += __shfl_xor_sync(~0u, l, of);
#pragma unroll
    for (int d = 0; d < 32; d++) o[d] += __shfl_xor_sync(~0u, o[d], of);
  }
  float mine = 0.f;
#pragma unroll
  for (int d = 0; d < 32; d++) if (lane == d) mine = o[d];
  orow[lane] = __float2bfloat16(mine / l);
}

constexpr int QKV_ST = 5, QKV_STAGE = A_BYTES + 2 * B_CHUNK;
constexpr int FR_KV = QKV_ST * QKV_STAGE;
constexpr int FR_Q = FR_KV + 16384;
constexpr int FR_MOD = FR_Q + 32768;
constexpr int FR_KVS = FR_MOD + 8192;
constexpr int FR_ONE = FR_KVS + 2048;
constexpr int FR_SC = FR_ONE + 1024;
constexpr int FR_BAR = FR_SC + 512, FRONT_SMEM = FR_BAR + 256;

__global__ void __launch_bounds__(FRONT_THREADS, 1)
front_kernel(const __grid_constant__ CUtensorMap mA, const __grid_constant__ CUtensorMap mWq, const __grid_constant__ CUtensorMap mWk,
             const __grid_constant__ CUtensorMap mWv, const __grid_constant__ CUtensorMap mKs, const __grid_constant__ CUtensorMap mVs,
             const __grid_constant__ CUtensorMap mK, const __grid_constant__ CUtensorMap mV, const __grid_constant__ CUtensorMap mOs,
             const bf16* __restrict__ x, const bf16* __restrict__ cond, const bf16* __restrict__ wmod,
             const bf16* __restrict__ w_o, const bf16* __restrict__ w_g, const bf16* __restrict__ w_u) {
  extern __shared__ __align__(1024) uint8_t smem[];
  const uint32_t base = smem_u32(smem), bars = base + FR_BAR;
  const uint32_t full0 = bars, empty0 = full0 + 8 * QKV_ST;
  const uint32_t afull0 = empty0 + 8 * QKV_ST, aempty0 = afull0 + 8 * ATT_SLOTS;
  const uint32_t h1rdy = aempty0 + 8 * ATT_SLOTS, w1done = h1rdy + 8, pub2 = w1done + 8, xfull = pub2 + 8, kvfull = xfull + 8;
  const uint32_t kvpub = kvfull + 8, kvrdy = kvpub + 8;
  const int tid = threadIdx.x, wg = __shfl_sync(~0u, tid >> 7, 0);
  const int b = blockIdx.x, mt = b >> 3, nt = b & 7;
  if (b >= 128) {
    float* sc = reinterpret_cast<float*>(smem);
    float* red = sc + DM;
    for (int i = tid; i < DM; i += FRONT_THREADS) { const float cc = __bfloat162float(cond[i]); sc[i] = cc / (1.f + __expf(-cc)); }
    __syncthreads();
    pdl_launch();
    if (tid < 512) {
      const int ch = tid & 127, rg = tid >> 7;
      const bf16* wp = wmod + (size_t)(rg * 256) * (6 * DM) + 2 * DM + (b - 128) * 1024 + ch * 8;
      float a[8];
#pragma unroll
      for (int j = 0; j < 8; j++) a[j] = 0.f;
#pragma unroll 1
      for (int r = 0; r < 256; r += 8) {
        uint4 v[8];
#pragma unroll
        for (int i = 0; i < 8; i++) v[i] = ldg_stream(wp + (size_t)(r + i) * (6 * DM));
#pragma unroll
        for (int i = 0; i < 8; i++) {
          const float sv = sc[rg * 256 + r + i];
          a[0] += sv * bf_lo(v[i].x); a[1] += sv * bf_hi(v[i].x); a[2] += sv * bf_lo(v[i].y); a[3] += sv * bf_hi(v[i].y);
          a[4] += sv * bf_lo(v[i].z); a[5] += sv * bf_hi(v[i].z); a[6] += sv * bf_lo(v[i].w); a[7] += sv * bf_hi(v[i].w);
        }
      }
      *reinterpret_cast<float4*>(red + rg * 1024 + ch * 8) = make_float4(a[0], a[1], a[2], a[3]);
      *reinterpret_cast<float4*>(red + rg * 1024 + ch * 8 + 4) = make_float4(a[4], a[5], a[6], a[7]);
    }
    __syncthreads();
    for (int i = tid; i < 1024; i += FRONT_THREADS) g_small.mod2[(b - 128) * 1024 + i] = red[i] + red[1024 + i] + red[2048 + i] + red[3072 + i];
    __syncthreads();
    if (tid == 0) asm volatile("red.release.gpu.global.add.u32 [%0], 1;" ::"l"(&g_flags[F_MOD2]) : "memory");
    return;
  }
  uint2 cv = make_uint2(0, 0);
  uint4 w1[4];
  if (tid < 512) {
    cv = __ldg(reinterpret_cast<const uint2*>(cond + (tid & 31) * 4 + (b >> 4) * 128));
    const bf16* wp = wmod + (size_t)((b >> 4) * 128 + (tid >> 4)) * (6 * DM) + (b & 15) * 128 + (tid & 15) * 8;
#pragma unroll
    for (int i = 0; i < 4; i++) w1[i] = ldg_stream(wp + (size_t)i * 32 * (6 * DM));
  } else {
#pragma unroll
    for (int i = 0; i < 4; i++) w1[i] = make_uint4(0, 0, 0, 0);
  }
  if (tid == 0) {
    for (int s = 0; s < QKV_ST; s++) { mbar_init(full0 + 8 * s, 1); mbar_init(empty0 + 8 * s, 2); }
    for (int s = 0; s < ATT_SLOTS; s++) { mbar_init(afull0 + 8 * s, 1); mbar_init(aempty0 + 8 * s, ATT_WG * 4); }
    mbar_init(h1rdy, 1); mbar_init(w1done, 1); mbar_init(pub2, 16); mbar_init(xfull, 1); mbar_init(kvfull, 1);
    mbar_init(kvpub, 8); mbar_init(kvrdy, 1);
    fence_bar_init();
  }
  if (tid < 64) *reinterpret_cast<uint4*>(smem + FR_ONE + tid * 16) = make_uint4(0x00003F80u, 0, 0, 0);
  fence_async_smem();
  __syncthreads();
  if (wg == ATT_WG) {
    reg_dec<40>();
    const int warp = __shfl_sync(~0u, (tid >> 5) & 3, 0), lane = tid & 31;
    if (warp == 0) {
      if (lane == 0) {
        const CUtensorMap* mkv = nt < 4 ? &mWk : &mWv;
        const int kvc = (nt & 3) * 8;
        mbar_expect_tx(xfull, 32768);
        bulk_load(base, x + (size_t)b * 16 * DM, 16384, xfull);
        bulk_load(base + QKV_STAGE, x + (size_t)(b * 16 + 8) * DM, 16384, xfull);
        mbar_wait(w1done, 0);
        mbar_expect_tx(kvfull, 16384);
        for (int q = 0; q < 4; q++) tma_load(base + FR_KV + q * 4096, mkv, kvc, q * 256, kvfull);
        Ring r{0, 1};
        for (int k = 0; k < DM / 64; k++) {
          mbar_wait(empty0 + 8 * r.s, r.ph);
          const uint32_t bar = full0 + 8 * r.s, dst = base + r.s * QKV_STAGE;
          mbar_expect_tx(bar, QKV_STAGE);
          tma_load(dst + A_BYTES, &mWq, nt * 128, k * 64, bar);
          tma_load(dst + A_BYTES + B_CHUNK, &mWq, nt * 128 + 64, k * 64, bar);
          if (k >= QKV_ST) tma_load(dst, &mA, k * 64, mt * 128, bar);
          ring_next<QKV_ST>(r);
          if (k == QKV_ST - 1) {
            if (mt >= QKV_ST) { tma_prefetch(&mWq, nt * 128, mt * 64); tma_prefetch(&mWq, nt * 128 + 64, mt * 64); }
            mbar_wait(h1rdy, 0);
            for (int q = 0; q < QKV_ST; q++) tma_load(base + q * QKV_STAGE, &mA, q * 64, mt * 128, full0 + 8 * q);
          }
        }
        mbar_wait(kvrdy, 0);
        Ring a{0, 1};
        for (int it = 0; it < 16; it++) {
          mbar_wait(aempty0 + 8 * a.s, a.ph);
          mbar_expect_tx(afull0 + 8 * a.s, ATT_SLOT);
          tma_load(base + a.s * ATT_SLOT, &mK, 0, (it & 7) * 256, afull0 + 8 * a.s);
          tma_load(base + a.s * ATT_SLOT + 16384, &mV, 0, (it & 7) * 256, afull0 + 8 * a.s);
          if (it == 8) l2_prefetch(w_o + (size_t)b * (DM * DM / 128), DM * DM / 128 * 2);
          if (it >= 2 && it < 10) {
            const int p = it - 2;
            l2_prefetch((p < 4 ? w_g : w_u) + (size_t)b * (DM * FF / 128) + (p & 3) * (DM * FF / 512), DM * FF / 512 * 2);
          }
          ring_next<ATT_SLOTS>(a);
        }
      }
    } else if (warp == 1) {
      if (lane == 0) {
        flag_wait(&g_pre[mt], 8);
        fence_async_global();
        mbar_arrive(h1rdy);
        flag_wait(&g_pre[16], 128);
        fence_async_global();
        mbar_arrive(kvrdy);
      }
    } else if (warp == 2) {
      if (lane == 0) {
        mbar_wait(pub2, 0);
        bulk_store(g_h1 + (size_t)b * 16 * DM, base, 16384);
        bulk_store(g_h1 + (size_t)(b * 16 + 8) * DM, base + QKV_STAGE, 16384);
        tma_store_commit();
        tma_store_wait_all();
        flag_add(&g_pre[mt]);
        mbar_wait(kvpub, 0);
        tma_store(nt < 4 ? &mKs : &mVs, base + FR_KVS, (nt & 3) * 8, mt * 128);
        tma_store_commit();
        tma_store_wait_all();
        flag_add(&g_pre[16]);
      }
    } else {
      for (int i = lane; i < 128; i += 32) g_stats[b * 128 + i] = make_float2(0.f, -1.f);
      asm volatile("fence.acq_rel.gpu;" ::: "memory");
      __syncwarp();
      if (lane == 0) pdl_launch();
    }
  } else {
    reg_inc<104>();
    const int lane = tid & 31, wv = tid >> 5;
    const int kq = b >> 4, cg = b & 15;
    float* sc = reinterpret_cast<float*>(smem + FR_SC);
    float* sm_mod = reinterpret_cast<float*>(smem + FR_MOD);
    auto dot8 = [](float (&a)[8], float s, const uint4& v) {
      a[0] += s * bf_lo(v.x); a[1] += s * bf_hi(v.x); a[2] += s * bf_lo(v.y); a[3] += s * bf_hi(v.y);
      a[4] += s * bf_lo(v.z); a[5] += s * bf_hi(v.z); a[6] += s * bf_lo(v.w); a[7] += s * bf_hi(v.w);
    };
    {
      if (tid < 32) {
        const float c0 = bf_lo(cv.x), c1 = bf_hi(cv.x), c2 = bf_lo(cv.y), c3 = bf_hi(cv.y);
        *reinterpret_cast<float4*>(sc + tid * 4) = make_float4(c0 / (1.f + __expf(-c0)), c1 / (1.f + __expf(-c1)), c2 / (1.f + __expf(-c2)), c3 / (1.f + __expf(-c3)));
      }
      named_bar(1, 512);
      float a[8];
#pragma unroll
      for (int j = 0; j < 8; j++) a[j] = 0.f;
#pragma unroll
      for (int i = 0; i < 4; i++) dot8(a, sc[(tid >> 4) + 32 * i], w1[i]);
      pin(a);
      if (tid == 0) mbar_arrive(w1done);
#pragma unroll
      for (int j = 0; j < 8; j++) a[j] += __shfl_xor_sync(~0u, a[j], 16);
      if (lane < 16) {
        *reinterpret_cast<float4*>(sm_mod + wv * 128 + lane * 8) = make_float4(a[0], a[1], a[2], a[3]);
        *reinterpret_cast<float4*>(sm_mod + wv * 128 + lane * 8 + 4) = make_float4(a[4], a[5], a[6], a[7]);
      }
      named_bar(1, 512);
      if (tid < 128) {
        float t = 0.f;
#pragma unroll
        for (int w = 0; w < 16; w++) t += sm_mod[w * 128 + tid];
        asm volatile("st.relaxed.gpu.global.u32 [%0], %1;" ::"l"(&g_small.mod1[kq][cg * 128 + tid]), "r"(__float_as_uint(t) + 1u) : "memory");
      }
    }
    {
      float f[32];
      uint8_t* xrow = smem + (wv >> 3) * QKV_STAGE + (wv & 7) * 2048 + lane * 16;
      mbar_wait(xfull, 0);
#pragma unroll
      for (int i = 0; i < 4; i++) {
        const uint4 v = *reinterpret_cast<const uint4*>(xrow + i * 512);
        f[8 * i + 0] = bf_lo(v.x); f[8 * i + 1] = bf_hi(v.x); f[8 * i + 2] = bf_lo(v.y); f[8 * i + 3] = bf_hi(v.y);
        f[8 * i + 4] = bf_lo(v.z); f[8 * i + 5] = bf_hi(v.z); f[8 * i + 6] = bf_lo(v.w); f[8 * i + 7] = bf_hi(v.w);
      }
      float t = 0.f;
#pragma unroll
      for (int i = 0; i < 32; i++) t += f[i];
#pragma unroll
      for (int o = 16; o > 0; o >>= 1) t += __shfl_xor_sync(~0u, t, o);
      const float mean = t * (1.f / DM);
      float q = 0.f;
#pragma unroll
      for (int i = 0; i < 32; i++) { f[i] -= mean; q += f[i] * f[i]; }
#pragma unroll
      for (int o = 16; o > 0; o >>= 1) q += __shfl_xor_sync(~0u, q, o);
      const float rs = rsqrtf(q * (1.f / DM) + 1e-5f);
      uint4 u[8];
#pragma unroll
      for (int qq = 0; qq < 8; qq++) u[qq] = make_uint4(0, 0, 0, 0);
      uint32_t pending = 0xffu;
      int it = 0;
#pragma unroll 1
      while (pending) {
#pragma unroll
        for (int qq = 0; qq < 8; qq++)
          if (pending & (1u << qq))
            asm volatile("ld.relaxed.gpu.global.v4.u32 {%0, %1, %2, %3}, [%4];" : "=r"(u[qq].x), "=r"(u[qq].y), "=r"(u[qq].z), "=r"(u[qq].w)
                         : "l"(&g_small.mod1[qq][tid * 4]) : "memory");
#pragma unroll
        for (int qq = 0; qq < 8; qq++)
          if (u[qq].x && u[qq].y && u[qq].z && u[qq].w) pending &= ~(1u << qq);
        if (++it > (1 << 22)) __trap();
      }
      float4 sum = make_float4(0.f, 0.f, 0.f, 0.f);
#pragma unroll
      for (int qq = 0; qq < 8; qq++) {
        sum.x += __uint_as_float(u[qq].x - 1u); sum.y += __uint_as_float(u[qq].y - 1u);
        sum.z += __uint_as_float(u[qq].z - 1u); sum.w += __uint_as_float(u[qq].w - 1u);
      }
      float* vecs = reinterpret_cast<float*>(smem + FR_Q);
      reinterpret_cast<float4*>(vecs)[tid] = sum;
      named_bar(1, 512);
#pragma unroll
      for (int i = 0; i < 4; i++) {
        const int col = (i * 32 + lane) * 8;
        const float4 a0 = *reinterpret_cast<const float4*>(vecs + DM + col), a1 = *reinterpret_cast<const float4*>(vecs + DM + col + 4);
        const float4 b0 = *reinterpret_cast<const float4*>(vecs + col), b1 = *reinterpret_cast<const float4*>(vecs + col + 4);
        const float* v = &f[8 * i];
        uint4 o;
        o.x = pack_bf16(v[0] * rs * (1.f + a0.x) + b0.x, v[1] * rs * (1.f + a0.y) + b0.y);
        o.y = pack_bf16(v[2] * rs * (1.f + a0.z) + b0.z, v[3] * rs * (1.f + a0.w) + b0.w);
        o.z = pack_bf16(v[4] * rs * (1.f + a1.x) + b1.x, v[5] * rs * (1.f + a1.y) + b1.y);
        o.w = pack_bf16(v[6] * rs * (1.f + a1.z) + b1.z, v[7] * rs * (1.f + a1.w) + b1.w);
        *reinterpret_cast<uint4*>(xrow + i * 512) = o;
      }
      fence_async_smem();
      __syncwarp();
      if (lane == 0) mbar_arrive(pub2);
    }
    if (wg < 2) {
      float acc[64], akv[4];
      const bool elect = (tid & 127) == 0;
      const uint64_t da0 = mkdesc(base + wg * 8192, 16, 1024, 1), db0 = mkdesc(base + A_BYTES, B_CHUNK, 1024, 1);
      const uint64_t dkv0 = mkdesc(base + FR_KV, 128, 128, 0);
      Ring r{0, 0};
      uint32_t prev = 0;
      mbar_wait(kvfull, 0);
#pragma unroll 1
      for (int k = 0; k < DM / 64; k++) {
        mbar_wait(full0 + 8 * r.s, r.ph);
        const uint64_t da = da0 + (uint64_t)(r.s * (QKV_STAGE >> 4)), db = db0 + (uint64_t)(r.s * (QKV_STAGE >> 4));
        const uint64_t dkv = dkv0 + (uint64_t)(k * 64);
        wg_fence();
#pragma unroll
        for (int j = 0; j < 4; j++) {
          wg_ss_n128_mn(acc, da + j * 2, db + j * 128, (k > 0 || j > 0) ? 1 : 0);
          wg_ss_n8_mn(akv, da + j * 2, dkv + j * 16, (k > 0 || j > 0) ? 1 : 0);
        }
        wg_commit();
        wg_wait<1>();
        if (k > 0 && elect) mbar_arrive(empty0 + 8 * prev);
        prev = r.s;
        ring_next<QKV_ST>(r);
      }
      wg_wait<0>();
      pin(acc); pin(akv);
      const int rl = wg * 64 + (wv & 3) * 16 + (lane >> 2), c = lane & 3;
      *reinterpret_cast<uint32_t*>(smem + FR_KVS + rl * 16 + c * 4) = pack_bf16(akv[0], akv[1]);
      *reinterpret_cast<uint32_t*>(smem + FR_KVS + (rl + 8) * 16 + c * 4) = pack_bf16(akv[2], akv[3]);
      fence_async_smem();
      __syncwarp();
      if (lane == 0) mbar_arrive(kvpub);
      constexpr float QS = 1.4426950408889634f * 0.17677669529663687f;
#pragma unroll
      for (int hh = 0; hh < 4; hh++) {
        uint4 lo, hi;
        lo.x = pack_bf16(acc[16 * hh + 0] * QS, acc[16 * hh + 1] * QS);  hi.x = pack_bf16(acc[16 * hh + 2] * QS, acc[16 * hh + 3] * QS);
        lo.y = pack_bf16(acc[16 * hh + 4] * QS, acc[16 * hh + 5] * QS);  hi.y = pack_bf16(acc[16 * hh + 6] * QS, acc[16 * hh + 7] * QS);
        lo.z = pack_bf16(acc[16 * hh + 8] * QS, acc[16 * hh + 9] * QS);  hi.z = pack_bf16(acc[16 * hh + 10] * QS, acc[16 * hh + 11] * QS);
        lo.w = pack_bf16(acc[16 * hh + 12] * QS, acc[16 * hh + 13] * QS); hi.w = pack_bf16(acc[16 * hh + 14] * QS, acc[16 * hh + 15] * QS);
        uint8_t* qt = smem + FR_Q + (hh * 2 + wg) * 4096 + ((wv & 3) * 16 + (lane >> 2)) * 64 + c * 16;
        *reinterpret_cast<uint4*>(qt) = lo;
        *reinterpret_cast<uint4*>(qt + 8 * 64) = hi;
      }
    }
    named_bar(1, 512);

    const int warp = wv & 3, g = lane >> 2, c = lane & 3;
    uint32_t cs = 0, cph = 0, rs = 0;
    const uint32_t cst = base + FR_ONE;
    const uint64_t kd0 = mkdesc(base, 16, 512, 2), vd0 = mkdesc(base + 16384, cst - (base + 16384), 512, 2);
    constexpr uint64_t KSLOT = ATT_SLOT >> 4, VSLOT = (uint64_t)(ATT_SLOT >> 4) - ((uint64_t)(ATT_SLOT >> 4) << 16);
    constexpr uint64_t VSTEP = 64ull - (64ull << 16), K32 = 128;
    uint8_t* ostg = smem + FR_KV + wg * 4096;
#pragma unroll 1
    for (int pass = 0; pass < 2; pass++) {
      const int tile = pass * ATT_WG + wg;
      const uint8_t* qt = smem + FR_Q + tile * 4096 + (warp * 16 + g) * 64 + c * 16;
      const uint4 qa = *reinterpret_cast<const uint4*>(qt), qb = *reinterpret_cast<const uint4*>(qt + 8 * 64);
      float Sa[16], Sb[16], Oa[20];
      uint32_t P[8];
#pragma unroll
      for (int i = 0; i < 20; i++) Oa[i] = 0.f;
#pragma unroll
      for (int i = 0; i < 8; i++) P[i] = 0;
      float nm0, nm1, bz0, bz1;
      mbar_wait(afull0 + 8 * cs, cph);
      uint64_t kd = kd0 + cs * KSLOT, vd = vd0 + cs * VSLOT;
      if (++cs == ATT_SLOTS) { cs = 0; cph ^= 1; }
      wg_fence();
      wg_rs_n32_k(Sa, qa.x, qb.x, qa.y, qb.y, kd, 0); wg_rs_n32_k(Sa, qa.z, qb.z, qa.w, qb.w, kd + 2, 1);
      wg_rs_n32_k(Sb, qa.x, qb.x, qa.y, qb.y, kd + K32, 0); wg_rs_n32_k(Sb, qa.z, qb.z, qa.w, qb.w, kd + K32 + 2, 1);
      wg_commit();
      wg_wait<0>(); pin(Sa); pin(Sb);
      {
        float m0 = Sa[0], m1 = Sa[2];
#pragma unroll
        for (int j = 0; j < 4; j++) {
          m0 = fmaxf(m0, fmaxf(fmaxf(Sa[4 * j], Sa[4 * j + 1]), fmaxf(Sb[4 * j], Sb[4 * j + 1])));
          m1 = fmaxf(m1, fmaxf(fmaxf(Sa[4 * j + 2], Sa[4 * j + 3]), fmaxf(Sb[4 * j + 2], Sb[4 * j + 3])));
        }
        m0 = fmaxf(m0, __shfl_xor_sync(~0u, m0, 1)); m0 = fmaxf(m0, __shfl_xor_sync(~0u, m0, 2));
        m1 = fmaxf(m1, __shfl_xor_sync(~0u, m1, 1)); m1 = fmaxf(m1, __shfl_xor_sync(~0u, m1, 2));
        m0 = ceilf(m0) + ATT_MARGIN; m1 = ceilf(m1) + ATT_MARGIN;
        nm0 = -m0; nm1 = -m1; bz0 = (127.f - m0) * (1.0f / EXP_R); bz1 = (127.f - m1) * (1.0f / EXP_R);
      }
#define PVK(kk, VD) wg_rs_n40_mn(Oa, P[4 * kk], P[4 * kk + 1], P[4 * kk + 2], P[4 * kk + 3], (VD) + (kk) * VSTEP, 1)
#define ATT_STEP(SC, SN, KN, VD, DOQK, H) {                                                                                   \
        wg_wait<1>(); pin(SC);                                                                                                \
        softmax8<(ATT_PM >> (16 * H)) & 0xF>(&SC[0], &P[0], nm0, nm1, bz0, bz1); pinu<4>(&P[0]);                              \
        wg_fence(); PVK(0, VD);                                                                                               \
        if (DOQK) { wg_rs_n32_k(SN, qa.x, qb.x, qa.y, qb.y, KN, 0); wg_rs_n32_k(SN, qa.z, qb.z, qa.w, qb.w, (KN) + 2, 1); }   \
        wg_commit();                                                                                                          \
        wg_wait<1>();                                                                                                         \
        softmax8<(ATT_PM >> (16 * H + 8)) & 0xF>(&SC[8], &P[4], nm0, nm1, bz0, bz1); pinu<4>(&P[4]);                          \
        wg_fence(); PVK(1, VD); wg_commit(); }
#define ATT_REL() { if (lane == 0) mbar_arrive(aempty0 + 8 * rs); rs = (rs + 1) & (ATT_SLOTS - 1); }
      uint64_t vdn = vd;
#pragma unroll 1
      for (int j = 0; j < 7; j++) {
        ATT_STEP(Sa, Sb, kd + 1 * K32, vd, 1, 0)
        ATT_STEP(Sb, Sa, kd + 2 * K32, vd + 2 * VSTEP, 1, 1)
        if (j > 0) ATT_REL()
        ATT_STEP(Sa, Sb, kd + 3 * K32, vd + 4 * VSTEP, 1, 0)
        ATT_STEP(Sb, Sa, kd + 4 * K32, vd + 6 * VSTEP, 1, 1)
        ATT_STEP(Sa, Sb, kd + 5 * K32, vd + 8 * VSTEP, 1, 0)
        ATT_STEP(Sb, Sa, kd + 6 * K32, vd + 10 * VSTEP, 1, 1)
        ATT_STEP(Sa, Sb, kd + 7 * K32, vd + 12 * VSTEP, 1, 0)
        mbar_wait(afull0 + 8 * cs, cph);
        kd = kd0 + cs * KSLOT; vdn = vd0 + cs * VSLOT;
        if (++cs == ATT_SLOTS) { cs = 0; cph ^= 1; }
        ATT_STEP(Sb, Sa, kd, vd + 14 * VSTEP, 1, 1)
        vd = vdn;
      }
      ATT_STEP(Sa, Sb, kd + 1 * K32, vd, 1, 0)
      ATT_STEP(Sb, Sa, kd + 2 * K32, vd + 2 * VSTEP, 1, 1)
      ATT_REL()
      ATT_STEP(Sa, Sb, kd + 3 * K32, vd + 4 * VSTEP, 1, 0)
      ATT_STEP(Sb, Sa, kd + 4 * K32, vd + 6 * VSTEP, 1, 1)
      ATT_STEP(Sa, Sb, kd + 5 * K32, vd + 8 * VSTEP, 1, 0)
      ATT_STEP(Sb, Sa, kd + 6 * K32, vd + 10 * VSTEP, 1, 1)
      ATT_STEP(Sa, Sb, kd + 7 * K32, vd + 12 * VSTEP, 1, 0)
      ATT_STEP(Sb, Sa, kd, vd + 14 * VSTEP, 0, 1)
      wg_wait<0>(); pin(Oa);
      ATT_REL()
      const float l0 = __shfl_sync(~0u, Oa[16], lane & ~3), l1 = __shfl_sync(~0u, Oa[18], lane & ~3);
      const float i0 = 1.0f / l0, i1 = 1.0f / l1;
      bool ok0 = (l0 < ATT_LMAX) && (l0 > 0.f), ok1 = (l1 < ATT_LMAX) && (l1 > 0.f);
#pragma unroll
      for (int i = 0; i < 16; i++) {
        Oa[i] *= (i & 2) ? i1 : i0;
        const bool fin = fabsf(Oa[i]) <= 3.0e38f;
        if (i & 2) ok1 = ok1 && fin; else ok0 = ok0 && fin;
      }
      const uint32_t bad0 = __ballot_sync(~0u, !ok0), bad1 = __ballot_sync(~0u, !ok1);
      if (pass == 1) { if ((tid & 127) == 0) tma_store_wait_read(); named_bar(3 + wg, 128); }
#pragma unroll
      for (int j = 0; j < 4; j++) {
        *reinterpret_cast<uint32_t*>(ostg + (warp * 16 + g) * 64 + 16 * j + 4 * c) = pack_bf16(Oa[4 * j], Oa[4 * j + 1]);
        *reinterpret_cast<uint32_t*>(ostg + (warp * 16 + g + 8) * 64 + 16 * j + 4 * c) = pack_bf16(Oa[4 * j + 2], Oa[4 * j + 3]);
      }
      if (bad0 | bad1) {
        __syncwarp();
#pragma unroll 1
        for (int rr = 0; rr < 16; rr++) {
          if (((rr < 8 ? bad0 >> (4 * rr) : bad1 >> (4 * (rr - 8))) & 0xFu) == 0) continue;
          attn_row_exact(reinterpret_cast<const uint4*>(smem + FR_Q + tile * 4096 + (warp * 16 + rr) * 64),
                         reinterpret_cast<bf16*>(ostg + (warp * 16 + rr) * 64), lane);
        }
      }
      fence_async_smem();
      named_bar(3 + wg, 128);
      if ((tid & 127) == 0) {
        tma_store(&mOs, smem_u32(ostg), (nt * 4 + (tile >> 1)) * DH, mt * 128 + (tile & 1) * 64);
        tma_store_commit();
        if (pass == 1) { tma_store_wait_all(); flag_add(&g_flags[F_ATT + mt]); }
      }
    }
  }
}

constexpr int PS = 4, PSTAGE = A_BYTES + 4 * B_CHUNK;
constexpr int POST_VEC = PS * PSTAGE + 32768, POST_BAR = POST_VEC + 2048, POST_SMEM = POST_BAR + 256;

struct Pipe {
  uint32_t base, full0, empty0;
  Ring r;
};

template <int BN>
__device__ __forceinline__ void kblock(float (&acc)[BN / 2], Pipe& p, uint64_t da0, uint64_t db0, int first) {
  mbar_wait(p.full0 + 8 * p.r.s, p.r.ph);
  const uint64_t da = da0 + (uint64_t)(p.r.s * (PSTAGE >> 4)), db = db0 + (uint64_t)(p.r.s * (PSTAGE >> 4));
  wg_fence();
#pragma unroll
  for (int j = 0; j < 4; j++) Mma<BN>::go(acc, da + j * 2, db + j * 128, (first && j == 0) ? 0 : 1);
  wg_commit();
}
template <int BN, int NFILL, class Fill>
__device__ __forceinline__ void tile_loop(float (&acc)[BN / 2], int KT, Pipe& p, int wg, bool elect, Fill&& fill) {
  const uint64_t da0 = mkdesc(p.base + wg * 8192, 16, 1024, 1), db0 = mkdesc(p.base + A_BYTES, B_CHUNK, 1024, 1);
  uint32_t prev = 0;
#pragma unroll
  for (int k = 0; k < NFILL; k++) {
    kblock<BN>(acc, p, da0, db0, k == 0);
    fill(k);
    wg_wait<1>();
    if (k > 0 && elect) mbar_arrive(p.empty0 + 8 * prev);
    prev = p.r.s;
    ring_next<PS>(p.r);
  }
#pragma unroll 1
  for (int k = NFILL; k < KT; k++) {
    kblock<BN>(acc, p, da0, db0, 0);
    wg_wait<1>();
    if (elect) mbar_arrive(p.empty0 + 8 * prev);
    prev = p.r.s;
    ring_next<PS>(p.r);
  }
  wg_wait<0>();
  pin(acc);
  if (elect) mbar_arrive(p.empty0 + 8 * prev);
}
__device__ __forceinline__ float glu(float g, float u) { return u * rcp(1.f + ex2(g * -1.4426950408889634f)); }
__device__ __forceinline__ uint32_t glu2(uint32_t g, uint32_t u) { return pack_bf16(glu(bf_lo(g), bf_lo(u)), glu(bf_hi(g), bf_hi(u))); }
__device__ __forceinline__ float2 lds_f2(uint32_t a) { float2 v; asm volatile("ld.shared.v2.f32 {%0, %1}, [%2];" : "=f"(v.x), "=f"(v.y) : "r"(a)); return v; }
__device__ __forceinline__ uint32_t lds_u32(uint32_t a) { uint32_t v; asm volatile("ld.shared.u32 %0, [%1];" : "=r"(v) : "r"(a)); return v; }

__global__ void __launch_bounds__(GEMM_THREADS, 1)
post_kernel(const __grid_constant__ CUtensorMap mO, const __grid_constant__ CUtensorMap mWo, const __grid_constant__ CUtensorMap mX,
            const __grid_constant__ CUtensorMap mX1L, const __grid_constant__ CUtensorMap mX1S,
            const __grid_constant__ CUtensorMap mH2L, const __grid_constant__ CUtensorMap mH2S,
            const __grid_constant__ CUtensorMap mWg, const __grid_constant__ CUtensorMap mWu,
            const __grid_constant__ CUtensorMap mActL, const __grid_constant__ CUtensorMap mActS,
            const __grid_constant__ CUtensorMap mWd, const __grid_constant__ CUtensorMap mOut, const bf16* __restrict__ w_d) {
  extern __shared__ __align__(1024) uint8_t smem[];
  const uint32_t base = smem_u32(smem), stg = base + PS * PSTAGE, vec = base + POST_VEC, full0 = base + POST_BAR, empty0 = full0 + 8 * PS;
  const uint32_t stg_full = empty0 + 8 * PS, stg_free = stg_full + 8;
  const uint32_t st_ready = stg_free + 8, st_done = st_ready + 32;
  const uint32_t h2rdy = st_done + 16, actrdy = h2rdy + 64, ordy = actrdy + 32, modrdy = ordy + 8;
  const int tid = threadIdx.x, wg = __shfl_sync(~0u, tid >> 7, 0);
  const int mt = blockIdx.x >> 3, nj = blockIdx.x & 7;
  if (tid == 0) {
    for (int s = 0; s < PS; s++) { mbar_init(full0 + 8 * s, 1); mbar_init(empty0 + 8 * s, 2); }
    mbar_init(stg_full, 1); mbar_init(stg_free, 2);
    for (int w = 0; w < 2; w++) { mbar_init(st_ready + 16 * w, 4); mbar_init(st_ready + 16 * w + 8, 4); mbar_init(st_done + 8 * w, 1); }
    for (int i = 0; i < 14; i++) mbar_init(h2rdy + 8 * i, 1);
    fence_bar_init();
  }
  if (tid == 256) { prefetch_map(&mX); prefetch_map(&mWo); prefetch_map(&mO); prefetch_map(&mWg); prefetch_map(&mWu); prefetch_map(&mH2L); }
  __syncthreads();
  if (wg == 2) {
    reg_dec<40>();
    const int warp = __shfl_sync(~0u, (tid >> 5) & 3, 0);
    if ((tid & 31) == 0) {
      if (warp == 0) {
        Ring r{0, 1};
        auto acquire = [&](uint32_t bytes) { mbar_wait(empty0 + 8 * r.s, r.ph); mbar_expect_tx(full0 + 8 * r.s, bytes); };
        for (int k = 0; k < DM / 64; k++) {
          acquire(A_BYTES + 2 * B_CHUNK);
          const uint32_t dst = base + r.s * PSTAGE, bar = full0 + 8 * r.s;
          tma_load(dst + A_BYTES, &mWo, nj * 128, k * 64, bar);
          tma_load(dst + A_BYTES + B_CHUNK, &mWo, nj * 128 + 64, k * 64, bar);
          if (k >= PS) tma_load(dst, &mO, k * 64, mt * 128, bar);
          ring_next<PS>(r);
          if (k == PS - 1) {
            mbar_expect_tx(stg_full, 32768);
            tma_load(stg, &mX, nj * 128, mt * 128, stg_full);
            tma_load(stg + 16384, &mX, nj * 128 + 64, mt * 128, stg_full);
            mbar_wait(ordy, 0);
            for (int q = 0; q < PS; q++) tma_load(base + q * PSTAGE, &mO, q * 64, mt * 128, full0 + 8 * q);
          }
        }
        auto load_gu_b = [&](int t, int k) {
          const int col = nj * 448 + t * 128;
          const uint32_t dst = base + r.s * PSTAGE + A_BYTES, bar = full0 + 8 * r.s;
          if (t < 3) {
            acquire(PSTAGE);
            tma_load(dst, &mWg, col, k * 64, bar); tma_load(dst + B_CHUNK, &mWg, col + 64, k * 64, bar);
            tma_load(dst + 2 * B_CHUNK, &mWu, col, k * 64, bar); tma_load(dst + 3 * B_CHUNK, &mWu, col + 64, k * 64, bar);
          } else {
            acquire(A_BYTES + 2 * B_CHUNK);
            tma_load(dst, &mWg, col, k * 64, bar); tma_load(dst + B_CHUNK, &mWu, col, k * 64, bar);
          }
        };
        {
          const uint32_t s0 = r.s;
          for (int kk = 0; kk < PS; kk++) { load_gu_b(0, kk); ring_next<PS>(r); }
          for (int kk = 0; kk < PS; kk++) {
            if ((kk & 1) == 0) mbar_wait(h2rdy + 8 * (kk >> 1), 0);
            const uint32_t s = (s0 + kk) & (PS - 1);
            tma_load(base + s * PSTAGE, &mH2L, kk * 64, mt * 128, full0 + 8 * s);
          }
        }
        for (int t = 0; t < 4; t++)
          for (int kk = (t == 0 ? PS : 0); kk < DM / 64; kk++) {
            if (t == 1 && (kk & 3) == 0) l2_prefetch(w_d + (size_t)blockIdx.x * (DM * FF / 128) + (kk >> 2) * (DM * FF / 512), DM * FF / 512 * 2);
            load_gu_b(t, kk);
            if (t == 0 && (kk & 1) == 0) mbar_wait(h2rdy + 8 * (kk >> 1), 0);
            tma_load(base + r.s * PSTAGE, &mH2L, kk * 64, mt * 128, full0 + 8 * r.s);
            ring_next<PS>(r);
          }
        for (int t = 0; t < 4; t++) {
          const int per = t < 3 ? 2 : 1;
          for (int i = 0; i < 8 * per; i++) {
            const int col = (i / per) * 448 + t * 128 + (i % per) * 64;
            acquire(A_BYTES + 2 * B_CHUNK);
            const uint32_t dst = base + r.s * PSTAGE, bar = full0 + 8 * r.s;
            tma_load(dst + A_BYTES, &mWd, nj * 128, col, bar);
            tma_load(dst + A_BYTES + B_CHUNK, &mWd, nj * 128 + 64, col, bar);
            if (i == 0) mbar_wait(actrdy + 8 * t, 0);
            tma_load(dst, &mActL, col, mt * 128, bar);
            if (t == 2 && (i == 0 || i == 4)) tma_prefetch(&mX1L, nj * 128 + (i >> 2) * 64, mt * 128);
            ring_next<PS>(r);
          }
        }
        mbar_wait(stg_free, 0);
        mbar_expect_tx(stg_full, 32768);
        tma_load(stg, &mX1L, nj * 128, mt * 128, stg_full);
        tma_load(stg + 16384, &mX1L, nj * 128 + 64, mt * 128, stg_full);
      } else if (warp < 3) {
        const int w = warp - 1;
        const uint32_t src = stg + w * 8192;
        const int row = mt * 128 + w * 64;
        uint32_t ph[2] = {0, 0};
        auto put = [&](const CUtensorMap* m, int col, int halves, unsigned* flag) {
          for (int h = 0; h < halves; h++) {
            if (h == 0) { mbar_wait(st_ready + 16 * w, ph[0]); ph[0] ^= 1; } else { mbar_wait(st_ready + 16 * w + 8, ph[1]); ph[1] ^= 1; }
            tma_store(m, src + h * 16384, col + h * 64, row);
            tma_store_commit();
          }
          tma_store_wait_read();
          mbar_arrive(st_done + 8 * w);
          if (flag) { tma_store_wait_all(); flag_add(flag); }
        };
        if (w == 0) { flag_wait(&g_flags[F_MOD2], 4); mbar_arrive(modrdy); }
        put(&mX1S, nj * 128, 2, nullptr);
        put(&mH2S, nj * 128, 2, &g_flags[F_H2 + mt * 8 + nj]);
        for (int t = 0; t < 4; t++) put(&mActS, nj * 448 + t * 128, t < 3 ? 2 : 1, &g_flags[F_ACT + mt * 4 + t]);
        mbar_arrive(stg_free);
        put(&mOut, nj * 128, 2, nullptr);
      } else {
        flag_wait(&g_flags[F_ATT + mt], 32); fence_async_global(); mbar_arrive(ordy);
        for (int i = 0; i < 8; i++) { flag_wait(&g_flags[F_H2 + mt * 8 + i], 2); fence_async_global(); mbar_arrive(h2rdy + 8 * i); }
        for (int t = 0; t < 4; t++) { flag_wait(&g_flags[F_ACT + mt * 4 + t], 16); fence_async_global(); mbar_arrive(actrdy + 8 * t); }
        if (atomicAdd(&g_small.done, 1u) == 127u) {
          for (int i = 0; i < F_COUNT; i++) g_flags[i] = 0;
          for (int i = 0; i < 17; i++) g_pre[i] = 0;
          g_small.done = 0;
        }
        pdl_wait();
      }
    }
  } else {
    reg_inc<232>();
    const int lane = tid & 31, warp = (tid >> 5) & 3, g = lane >> 2, c = lane & 3;
    const int rl = wg * 64 + warp * 16;
    const bool elect = (tid & 127) == 0;
    Pipe p{base, full0, empty0, Ring{0, 0}};
    auto nofill = [](int) {};
    uint32_t st_ph = 0;
    auto staged = [&](int h) { fence_async_smem(); __syncwarp(); if (lane == 0) mbar_arrive(st_ready + 16 * wg + 8 * h); };
    auto staging_free = [&]() { mbar_wait(st_done + 8 * wg, st_ph); st_ph ^= 1; };
    mbar_wait(modrdy, 0);
    for (int i = tid; i < 512; i += 256) {
      const int v = i >> 7, col = nj * 128 + (i & 127);
      const float x = __ldcg(&g_small.mod2[(v == 0 ? 0 : v == 1 ? 2 : v == 2 ? 1 : 3) * DM + col]);
      reinterpret_cast<float*>(smem + POST_VEC)[i] = v == 1 ? 1.f + x : x;
    }
    named_bar(3, 256);
    mbar_wait(ordy, 0);
    if (tid < 128) (&g_small.mod1[0][0])[blockIdx.x * 128 + tid] = 0;
    const uint32_t vcol = vec + 8 * c;
    const uint32_t xoff = stg + (rl + g) * 128 + 4 * c;
    auto load_resid = [&](uint32_t (&x)[32], float2 (&v)[16], int vi) {
#pragma unroll
      for (int jb = 0; jb < 16; jb++) {
        const uint32_t a = xoff + (jb >> 3) * 16384 + (((jb & 7) ^ g) << 4);
        x[2 * jb] = lds_u32(a); x[2 * jb + 1] = lds_u32(a + 1024);
        v[jb] = lds_f2(vcol + 512 * vi + 32 * jb);
      }
    };

    {
      float acc[64];
      tile_loop<128, 1>(acc, DM / 64, p, wg, elect, nofill);
      float s0 = 0.f, s1 = 0.f;
      {
        uint32_t x[32]; float2 ga[16];
        mbar_wait(stg_full, 0);
        load_resid(x, ga, 0);
        __syncwarp();
#pragma unroll
        for (int j = 0; j < 16; j += 2) {
          uint32_t o[4];
#pragma unroll
          for (int t = 0; t < 2; t++) {
            const int jb = j + t;
            o[2 * t] = pack_bf16(bf_lo(x[2 * jb]) + ga[jb].x * acc[4 * jb], bf_hi(x[2 * jb]) + ga[jb].y * acc[4 * jb + 1]);
            o[2 * t + 1] = pack_bf16(bf_lo(x[2 * jb + 1]) + ga[jb].x * acc[4 * jb + 2], bf_hi(x[2 * jb + 1]) + ga[jb].y * acc[4 * jb + 3]);
            acc[4 * jb] = bf_lo(o[2 * t]); acc[4 * jb + 1] = bf_hi(o[2 * t]); acc[4 * jb + 2] = bf_lo(o[2 * t + 1]); acc[4 * jb + 3] = bf_hi(o[2 * t + 1]);
            s0 += acc[4 * jb] + acc[4 * jb + 1]; s1 += acc[4 * jb + 2] + acc[4 * jb + 3];
            x[2 * jb] = o[2 * t]; x[2 * jb + 1] = o[2 * t + 1];
          }
        }
        s0 += __shfl_xor_sync(~0u, s0, 1); s1 += __shfl_xor_sync(~0u, s1, 1);
        s0 += __shfl_xor_sync(~0u, s0, 2); s1 += __shfl_xor_sync(~0u, s1, 2);
        const float mu0 = s0 * (1.f / 128), mu1 = s1 * (1.f / 128);
        float q0 = 0.f, q1 = 0.f;
#pragma unroll
        for (int jb = 0; jb < 16; jb++) {
          const float a = acc[4 * jb] - mu0, b = acc[4 * jb + 1] - mu0, d = acc[4 * jb + 2] - mu1, e = acc[4 * jb + 3] - mu1;
          q0 += a * a + b * b; q1 += d * d + e * e;
        }
        q0 += __shfl_xor_sync(~0u, q0, 1); q1 += __shfl_xor_sync(~0u, q1, 1);
        q0 += __shfl_xor_sync(~0u, q0, 2); q1 += __shfl_xor_sync(~0u, q1, 2);
        const int row = mt * 128 + rl + g;
        if (c == 0) {
          asm volatile("st.relaxed.gpu.global.v2.f32 [%0], {%1, %2};" ::"l"(&g_stats[row * 8 + nj]), "f"(s0), "f"(q0) : "memory");
          asm volatile("st.relaxed.gpu.global.v2.f32 [%0], {%1, %2};" ::"l"(&g_stats[(row + 8) * 8 + nj]), "f"(s1), "f"(q1) : "memory");
        }
#pragma unroll
        for (int j = 0; j < 16; j += 2) {
          stage_store(stg, rl, lane, j, x[2 * j], x[2 * j + 1], x[2 * j + 2], x[2 * j + 3]);
          if (j == 6 || j == 14) staged(j >> 3);
        }
      }
      float2 sc[16], sh[16];
#pragma unroll
      for (int jb = 0; jb < 16; jb++) { sc[jb] = lds_f2(vcol + 512 + 32 * jb); sh[jb] = lds_f2(vcol + 1024 + 32 * jb); }
      float4 p0, p1;
      {
        const int row = mt * 128 + rl + g;
        const float4* a0 = reinterpret_cast<const float4*>(&g_stats[row * 8 + 2 * c]);
        const float4* a1 = reinterpret_cast<const float4*>(&g_stats[(row + 8) * 8 + 2 * c]);
        int it = 0;
#pragma unroll 1
        for (;; it++) {
          asm volatile("ld.relaxed.gpu.global.v2.f32 {%0, %1}, [%2];" : "=f"(p0.x), "=f"(p0.y) : "l"(a0) : "memory");
          asm volatile("ld.relaxed.gpu.global.v2.f32 {%0, %1}, [%2 + 8];" : "=f"(p0.z), "=f"(p0.w) : "l"(a0) : "memory");
          asm volatile("ld.relaxed.gpu.global.v2.f32 {%0, %1}, [%2];" : "=f"(p1.x), "=f"(p1.y) : "l"(a1) : "memory");
          asm volatile("ld.relaxed.gpu.global.v2.f32 {%0, %1}, [%2 + 8];" : "=f"(p1.z), "=f"(p1.w) : "l"(a1) : "memory");
          const bool ready = !(p0.y < 0.f) && !(p0.w < 0.f) && !(p1.y < 0.f) && !(p1.w < 0.f);
          if (__all_sync(~0u, ready)) break;
          if (it > (1 << 22)) __trap();
        }
      }
      float t0 = p0.x + p0.z, t1 = p1.x + p1.z;
      t0 += __shfl_xor_sync(~0u, t0, 1); t1 += __shfl_xor_sync(~0u, t1, 1);
      t0 += __shfl_xor_sync(~0u, t0, 2); t1 += __shfl_xor_sync(~0u, t1, 2);
      const float m0 = t0 * (1.f / DM), m1 = t1 * (1.f / DM);
      const float d0 = p0.x * (1.f / 128) - m0, d1 = p0.z * (1.f / 128) - m0, d2 = p1.x * (1.f / 128) - m1, d3 = p1.z * (1.f / 128) - m1;
      float v0 = p0.y + p0.w + 128.f * (d0 * d0 + d1 * d1), v1 = p1.y + p1.w + 128.f * (d2 * d2 + d3 * d3);
      v0 += __shfl_xor_sync(~0u, v0, 1); v1 += __shfl_xor_sync(~0u, v1, 1);
      v0 += __shfl_xor_sync(~0u, v0, 2); v1 += __shfl_xor_sync(~0u, v1, 2);
      const float r0 = rsqrtf(v0 * (1.f / DM) + 1e-5f), r1 = rsqrtf(v1 * (1.f / DM) + 1e-5f);
      staging_free();
#pragma unroll
      for (int j = 0; j < 16; j += 2) {
        uint32_t o[4];
#pragma unroll
        for (int t = 0; t < 2; t++) {
          const int jb = j + t;
          o[2 * t] = pack_bf16((acc[4 * jb] - m0) * r0 * sc[jb].x + sh[jb].x, (acc[4 * jb + 1] - m0) * r0 * sc[jb].y + sh[jb].y);
          o[2 * t + 1] = pack_bf16((acc[4 * jb + 2] - m1) * r1 * sc[jb].x + sh[jb].x, (acc[4 * jb + 3] - m1) * r1 * sc[jb].y + sh[jb].y);
        }
        stage_store(stg, rl, lane, j, o[0], o[1], o[2], o[3]);
        if (j == 6 || j == 14) staged(j >> 3);
      }
    }

    uint32_t pg[32], pu[32];
#pragma unroll
    for (int i = 0; i < 32; i++) { pg[i] = 0; pu[i] = 0; }
    bool have = false;
    auto glu_pair = [&](int q) {
      stage_store(stg, rl, lane, 2 * q, glu2(pg[4 * q], pu[4 * q]), glu2(pg[4 * q + 1], pu[4 * q + 1]),
                  glu2(pg[4 * q + 2], pu[4 * q + 2]), glu2(pg[4 * q + 3], pu[4 * q + 3]));
    };
#pragma unroll 1
    for (int t = 0; t < 3; t++) {
      float acc[128];
      tile_loop<256, 8>(acc, DM / 64, p, wg, elect, [&](int k) {
        if (have) {
          if (k == 0) staging_free();
          glu_pair(k);
          if (k == 3 || k == 7) staged(k >> 2);
        }
      });
#pragma unroll
      for (int i = 0; i < 32; i++) { pg[i] = pack_bf16(acc[2 * i], acc[2 * i + 1]); pu[i] = pack_bf16(acc[64 + 2 * i], acc[64 + 2 * i + 1]); }
      have = true;
    }
    {
      float acc[64];
      uint32_t half[2] = {0, 0};
      tile_loop<128, 16>(acc, DM / 64, p, wg, elect, [&](int k) {
        const uint32_t a = glu2(pg[2 * k], pu[2 * k]), b = glu2(pg[2 * k + 1], pu[2 * k + 1]);
        if (k == 1) staging_free();
        if (k & 1) stage_store(stg, rl, lane, k - 1, half[0], half[1], a, b); else { half[0] = a; half[1] = b; }
        if (k == 7 || k == 15) staged(k >> 3);
      });
#pragma unroll
      for (int i = 0; i < 16; i++) { pg[i] = pack_bf16(acc[2 * i], acc[2 * i + 1]); pu[i] = pack_bf16(acc[32 + 2 * i], acc[32 + 2 * i + 1]); }
    }
    {
      float acc[64];
      uint32_t half[2] = {0, 0};
      tile_loop<128, 10>(acc, FF / 64, p, wg, elect, [&](int k) {
        if (k >= 2) {
          const int q = k - 2;
          const uint32_t a = glu2(pg[2 * q], pu[2 * q]), b = glu2(pg[2 * q + 1], pu[2 * q + 1]);
          if (q == 1) staging_free();
          if (q & 1) stage_store(stg, rl, lane, q - 1, half[0], half[1], a, b); else { half[0] = a; half[1] = b; }
          if (q == 7) staged(0);
        }
      });
      uint32_t x[32]; float2 gb[16];
      mbar_wait(stg_full, 1);
      load_resid(x, gb, 3);
      __syncwarp();
#pragma unroll
      for (int j = 0; j < 16; j += 2) {
        uint32_t o[4];
#pragma unroll
        for (int t = 0; t < 2; t++) {
          const int jb = j + t;
          o[2 * t] = pack_bf16(bf_lo(x[2 * jb]) + gb[jb].x * acc[4 * jb], bf_hi(x[2 * jb]) + gb[jb].y * acc[4 * jb + 1]);
          o[2 * t + 1] = pack_bf16(bf_lo(x[2 * jb + 1]) + gb[jb].x * acc[4 * jb + 2], bf_hi(x[2 * jb + 1]) + gb[jb].y * acc[4 * jb + 3]);
        }
        stage_store(stg, rl, lane, j, o[0], o[1], o[2], o[3]);
        if (j == 6 || j == 14) staged(j >> 3);
      }
    }
  }
}

typedef CUresult (*EncodeFn)(CUtensorMap*, CUtensorMapDataType, cuuint32_t, void*, const cuuint64_t*, const cuuint64_t*, const cuuint32_t*,
                             const cuuint32_t*, CUtensorMapInterleave, CUtensorMapSwizzle, CUtensorMapL2promotion, CUtensorMapFloatOOBfill);
EncodeFn g_encode = nullptr;

CUtensorMap make_map(const void* p, uint64_t inner, uint64_t outer, uint32_t b0, uint32_t b1, CUtensorMapSwizzle sw) {
  CUtensorMap m;
  cuuint64_t dims[2] = {inner, outer}, str[1] = {inner * 2};
  cuuint32_t box[2] = {b0, b1}, es[2] = {1, 1};
  g_encode(&m, CU_TENSOR_MAP_DATA_TYPE_BFLOAT16, 2, const_cast<void*>(p), dims, str, box, es, CU_TENSOR_MAP_INTERLEAVE_NONE, sw,
           CU_TENSOR_MAP_L2_PROMOTION_L2_128B, CU_TENSOR_MAP_FLOAT_OOB_FILL_NONE);
  return m;
}

template <typename... KArgs, typename... Args>
void launch(void (*kern)(KArgs...), int grid, int block, int smem, bool pdl, Args... args) {
  cudaLaunchConfig_t cfg = {};
  cfg.gridDim = dim3(grid); cfg.blockDim = dim3(block); cfg.dynamicSmemBytes = smem; cfg.stream = cudaStreamPerThread;
  cudaLaunchAttribute at[1];
  at[0].id = cudaLaunchAttributeProgrammaticStreamSerialization;
  at[0].val.programmaticStreamSerializationAllowed = 1;
  cfg.attrs = at; cfg.numAttrs = pdl ? 1 : 0;
  cudaLaunchKernelEx(&cfg, kern, KArgs(args)...);
}
template <typename T> void* sym(T& s) { void* p = nullptr; cudaGetSymbolAddress(&p, s); return p; }

}

extern "C" void kernel_launch(void* const* d_in, const int* in_sizes, int n_in, void* d_out, int out_size) {
  const bf16* x = (const bf16*)d_in[0];
  const bf16* wq = (const bf16*)d_in[1];
  const bf16* wk = (const bf16*)d_in[2];
  const bf16* wv = (const bf16*)d_in[3];
  const bf16* wo = (const bf16*)d_in[4];
  const bf16* wg = (const bf16*)d_in[6];
  const bf16* wu = (const bf16*)d_in[7];
  const bf16* wd = (const bf16*)d_in[8];
  const bf16* cond = (const bf16*)d_in[9];
  const bf16* wmod = (const bf16*)d_in[10];
  bf16* out = (bf16*)d_out;

  if (!g_encode) {
    void* fn = nullptr;
    cudaDriverEntryPointQueryResult qr;
    cudaGetDriverEntryPoint("cuTensorMapEncodeTiled", &fn, cudaEnableDefault, &qr);
    g_encode = (EncodeFn)fn;
    cudaFuncSetAttribute(front_kernel, cudaFuncAttributeMaxDynamicSharedMemorySize, FRONT_SMEM);
    cudaFuncSetAttribute(post_kernel, cudaFuncAttributeMaxDynamicSharedMemorySize, POST_SMEM);
  }
  bf16 *h1 = (bf16*)sym(g_h1), *kk = (bf16*)sym(g_k), *vv = (bf16*)sym(g_v), *o = (bf16*)sym(g_o);
  bf16 *x1 = (bf16*)sym(g_x1), *h2 = (bf16*)sym(g_h2), *act = (bf16*)sym(g_act);
  const CUtensorMapSwizzle S128 = CU_TENSOR_MAP_SWIZZLE_128B, S64 = CU_TENSOR_MAP_SWIZZLE_64B;
  const CUtensorMap mH1 = make_map(h1, DM, SEQ, 64, 128, S128), mWq = make_map(wq, DM, DM, 64, 64, S128);
  const CUtensorMap mWk = make_map(wk, DH, DM, 8, 256, CU_TENSOR_MAP_SWIZZLE_NONE), mWv = make_map(wv, DH, DM, 8, 256, CU_TENSOR_MAP_SWIZZLE_NONE);
  const CUtensorMap mKs = make_map(kk, DH, SEQ, 8, 128, CU_TENSOR_MAP_SWIZZLE_NONE), mVs = make_map(vv, DH, SEQ, 8, 128, CU_TENSOR_MAP_SWIZZLE_NONE);
  const CUtensorMap mOs = make_map(o, DM, SEQ, 32, 64, CU_TENSOR_MAP_SWIZZLE_NONE);
  const CUtensorMap mK = make_map(kk, DH, SEQ, 32, 256, S64), mV = make_map(vv, DH, SEQ, 32, 256, S64);
  const CUtensorMap mO = make_map(o, DM, SEQ, 64, 128, S128), mWo = make_map(wo, DM, DM, 64, 64, S128);
  const CUtensorMap mX = make_map(x, DM, SEQ, 64, 128, S128);
  const CUtensorMap mX1L = make_map(x1, DM, SEQ, 64, 128, S128), mX1S = make_map(x1, DM, SEQ, 64, 64, S128);
  const CUtensorMap mH2L = make_map(h2, DM, SEQ, 64, 128, S128), mH2S = make_map(h2, DM, SEQ, 64, 64, S128);
  const CUtensorMap mWg = make_map(wg, FF, DM, 64, 64, S128), mWu = make_map(wu, FF, DM, 64, 64, S128);
  const CUtensorMap mActS = make_map(act, FF, SEQ, 64, 64, S128), mActL = make_map(act, FF, SEQ, 64, 128, S128);
  const CUtensorMap mWd = make_map(wd, DM, FF, 64, 64, S128), mOut = make_map(out, DM, SEQ, 64, 64, S128);

  launch(front_kernel, 132, FRONT_THREADS, FRONT_SMEM, false, mH1, mWq, mWk, mWv, mKs, mVs, mK, mV, mOs, x, cond, wmod, wo, wg, wu);
  launch(post_kernel, 128, GEMM_THREADS, POST_SMEM, true, mO, mWo, mX, mX1L, mX1S, mH2L, mH2S, mWg, mWu, mActL, mActS, mWd, mOut, wd);
}
```
